```python
import torch

def _softmax(x, axis=-1):
    return torch.softmax(x, dim=axis)
def _gelu(x):
    return torch.nn.functional.gelu(x, approximate="tanh")
def _silu(x):
    return torch.nn.functional.silu(x)
def _sigmoid(x):
    return torch.sigmoid(x)
def _layernorm(x, axis=-1, eps=1e-5):
    m = x.mean(dim=axis, keepdim=True)
    v = x.var(dim=axis, keepdim=True, unbiased=False)
    return (x - m) / torch.sqrt(v + eps)
def _scatter_add(tgt, idx, src, axis=0):
    return tgt.clone().index_add_(axis, idx, src)
def _segment_sum(src, seg, n):
    out = torch.zeros((n,) + src.shape[1:], dtype=src.dtype)
    return out.index_add_(0, seg, src)
def _pad(x, pw):
    flat = tuple(v for pair in reversed(pw) for v in pair)
    return torch.nn.functional.pad(x, flat)

kernel_name = 'gated_mix__softmax_full_mha__linear_kernel_hedgehog__prompt'

def setup_inputs():

    _w = (lambda a: (lambda t: t.to(torch.bfloat16) if t.is_floating_point() else t)(torch.as_tensor(a)))
    def _A_setup():
        B, S, D = 1, 2048, 640
        return {
            "x": _w((lambda *s: torch.randn(*s, dtype=torch.bfloat16) * 0.05)(B, S, D)),
            "wqkv": _w((lambda *s: torch.randn(*s, dtype=torch.bfloat16) * 0.8)(D, 3 * D)),
            "wo": _w((lambda *s: torch.randn(*s, dtype=torch.bfloat16) * 0.05)(D, D)),
        }
    _A_in = _A_setup()

    def _B_setup():
        B, S, D, H = 1, 2048, 640, 32
        Dh = D // H
        return {
            "x": _w((lambda *s: torch.randn(*s, dtype=torch.bfloat16) * 0.05)(B, S, D)),
            "wqkv": _w((lambda *s: torch.randn(*s, dtype=torch.bfloat16) * 1.6)(D, 3 * D)),
            "w_phi": _w((lambda *s: torch.randn(*s, dtype=torch.bfloat16) * 1.6)(H, Dh, Dh) * (Dh ** -0.5)),
            "wo": _w((lambda *s: torch.randn(*s, dtype=torch.bfloat16) * 0.05)(D, D)),
        }
    _B_in = _B_setup()

    return {
        "A_x": _A_in["x"],
        "A_wqkv": _A_in["wqkv"],
        "A_wo": _A_in["wo"],
        "B_x": _B_in["x"],
        "B_wqkv": _B_in["wqkv"],
        "B_w_phi": _B_in["w_phi"],
        "B_wo": _B_in["wo"],
        "gate_w": _w((lambda *s: torch.randn(*s, dtype=torch.bfloat16) * 0.05)(640) * 16.0),
    }

def reference(A_x, A_wqkv, A_wo, B_x, B_wqkv, B_w_phi, B_wo, gate_w):
    def _A_ref(x, wqkv, wo):
        B, S, D = x.shape
        H = 32; Dh = D // H
        qkv = (lambda x, *d: x.permute(*d))((x @ wqkv).reshape(B, S, 3, H, Dh), 2, 0, 3, 1, 4)
        q, k, v = qkv[0], qkv[1], qkv[2]
        scale = Dh ** -0.5
        scores = torch.einsum("bhqd,bhkd->bhqk", q, k) * scale
        p = _softmax(scores, axis=-1)
        o = torch.einsum("bhqk,bhkd->bhqd", p, v)
        return (lambda x, *d: x.permute(*d))(o, 0, 2, 1, 3).reshape(B, S, D) @ wo

    def _B_ref(x, wqkv, w_phi, wo):
        B, S, D = x.shape
        H = 32; Dh = D // H
        qkv = (lambda x, *d: x.permute(*d))((x @ wqkv).reshape(B, S, 3, H, Dh), 2, 0, 3, 1, 4)
        q, k, v = qkv[0], qkv[1], qkv[2]
        pq = torch.einsum("bhsd,hdf->bhsf", q, w_phi)
        pk = torch.einsum("bhsd,hdf->bhsf", k, w_phi)
        phi_q = torch.concatenate([_softmax(pq, axis=-1), _softmax(-pq, axis=-1)], axis=-1)
        phi_k = torch.concatenate([_softmax(pk, axis=-1), _softmax(-pk, axis=-1)], axis=-1)
        kv = torch.einsum("bhsf,bhsd->bhfd", phi_k, v)
        z  = torch.einsum("bhsf->bhf", phi_k)
        num = torch.einsum("bhqf,bhfd->bhqd", phi_q, kv)
        den = torch.einsum("bhqf,bhf->bhq", phi_q, z)[..., None] + 1e-6
        o = num / den
        return (lambda x, *d: x.permute(*d))(o, 0, 2, 1, 3).reshape(B, S, D) @ wo

    x = A_x
    g = _sigmoid((x * gate_w).sum(-1, keepdims=True))
    a = _A_ref(x, A_wqkv, A_wo)
    b = _B_ref(x, B_wqkv, B_w_phi, B_wo)
    return g * a + (1 - g) * b
```

```cpp
#include <cuda_runtime.h>
#include <cuda.h>
#include <cuda_bf16.h>
#include <stdint.h>

namespace {

constexpr int S_ = 2048, D_ = 640, H_ = 32;
constexpr uint32_t POLY_MASK = 0xD6D6u;
constexpr float L2E = 1.4426950408889634f;
constexpr uint32_t SPIN_LIMIT = 1u << 22;

__device__ uint4 g_kv[H_ * 32 * 6144 / 16];
__device__ uint4 g_q1[H_ * 128 * 32];
__device__ uint2 g_q2[H_ * 128 * 32];
__device__ float4 g_kvs[H_ * 240];
__device__ unsigned g_sync[16];
__device__ float4 g_kn2[H_ * 32];
__device__ int4 g_ve[8 * 32];
__device__ float g_gate[S_];
__device__ uint4 g_act[2][S_ * D_ / 8];
__device__ uint32_t g_konst[3] = {0u, 0u, 0x38003800u};
__device__ unsigned g_cnt[32];

#define TS(k, id) do {} while (0)
__device__ __forceinline__ uint32_t smem_u32(const void* p) { return (uint32_t)__cvta_generic_to_shared(p); }
__device__ __forceinline__ void mbar_init(uint32_t b, uint32_t c) {
  asm volatile("mbarrier.init.shared::cta.b64 [%0], %1;" ::"r"(b), "r"(c) : "memory");
}
__device__ __forceinline__ void mbar_expect(uint32_t b, uint32_t bytes) {
  asm volatile("mbarrier.arrive.expect_tx.shared::cta.b64 _, [%0], %1;" ::"r"(b), "r"(bytes) : "memory");
}
__device__ __forceinline__ void mbar_arrive(uint32_t b) {
  asm volatile("mbarrier.arrive.shared::cta.b64 _, [%0];" ::"r"(b) : "memory");
}
__device__ __forceinline__ void mbar_arrive_cta(uint32_t b, uint32_t cta) {
  asm volatile("{.reg .b32 r; mapa.shared::cluster.u32 r, %0, %1; mbarrier.arrive.shared::cluster.b64 _, [r];}" ::"r"(b),
               "r"(cta)
               : "memory");
}
__device__ __forceinline__ uint32_t mbar_try(uint32_t b, uint32_t par) {
  uint32_t ok;
  asm volatile("{.reg .pred p; mbarrier.try_wait.parity.shared::cta.b64 p, [%1], %2; selp.u32 %0, 1, 0, p;}"
               : "=r"(ok)
               : "r"(b), "r"(par)
               : "memory");
  return ok;
}
__device__ __forceinline__ uint32_t mbar_test(uint32_t b, uint32_t par) {
  uint32_t ok;
  asm volatile("{.reg .pred p; mbarrier.test_wait.parity.shared::cta.b64 p, [%1], %2; selp.u32 %0, 1, 0, p;}"
               : "=r"(ok)
               : "r"(b), "r"(par)
               : "memory");
  return ok;
}
__device__ __forceinline__ void mbar_wait(uint32_t b, uint32_t par) {
  if (!mbar_try(b, par)) {
    uint32_t n = 0;
    while (!mbar_try(b, par))
      if (++n > SPIN_LIMIT) break;
  }
}
__device__ __forceinline__ void mbar_wait_long(uint32_t b, uint32_t par) {
  uint32_t ok, n = 0;
  do {
    asm volatile("{.reg .pred p; mbarrier.try_wait.parity.shared::cta.b64 p, [%1], %2, 20000; selp.u32 %0, 1, 0, p;}"
                 : "=r"(ok)
                 : "r"(b), "r"(par)
                 : "memory");
  } while (!ok && ++n < (SPIN_LIMIT >> 8));
}
__device__ __forceinline__ void tma2(uint32_t dst, const CUtensorMap* m, int c0, int c1, uint32_t bar) {
  asm volatile(
      "cp.async.bulk.tensor.2d.shared::cluster.global.mbarrier::complete_tx::bytes [%0], [%1, {%3, %4}], [%2];" ::"r"(dst),
      "l"(m), "r"(bar), "r"(c0), "r"(c1)
      : "memory");
}
__device__ __forceinline__ void tma3_mc(uint32_t dst, const CUtensorMap* m, int c0, int c1, int c2, uint32_t bar) {
  asm volatile(
      "cp.async.bulk.tensor.3d.shared::cluster.global.mbarrier::complete_tx::bytes.multicast::cluster "
      "[%0], [%1, {%3, %4, %5}], [%2], %6;" ::"r"(dst),
      "l"(m), "r"(bar), "r"(c0), "r"(c1), "r"(c2), "h"((uint16_t)3)
      : "memory");
}
__device__ __forceinline__ void bulk_g2s(uint32_t dst, const void* src, uint32_t bytes, uint32_t bar) {
  asm volatile("cp.async.bulk.shared::cluster.global.mbarrier::complete_tx::bytes [%0], [%1], %2, [%3];" ::"r"(dst),
               "l"(src), "r"(bytes), "r"(bar)
               : "memory");
}
__device__ __forceinline__ void bulk_s2g(void* dst, uint32_t src, uint32_t bytes) {
  asm volatile("cp.async.bulk.global.shared::cta.bulk_group [%0], [%1], %2;" ::"l"(dst), "r"(src), "r"(bytes) : "memory");
}
__device__ __forceinline__ void prefetch_map(const CUtensorMap* m) {
  asm volatile("prefetch.tensormap [%0];" ::"l"(m) : "memory");
}
__device__ __forceinline__ void fence_async() { asm volatile("fence.proxy.async.shared::cta;" ::: "memory"); }
__device__ __forceinline__ void cluster_arrive() { asm volatile("barrier.cluster.arrive.relaxed.aligned;" ::: "memory"); }
__device__ __forceinline__ void cluster_wait() { asm volatile("barrier.cluster.wait.aligned;" ::: "memory"); }
__device__ __forceinline__ void bar_sync(int id, int n) { asm volatile("bar.sync %0, %1;" ::"r"(id), "r"(n) : "memory"); }
__device__ __forceinline__ void wg_fence() { asm volatile("wgmma.fence.sync.aligned;" ::: "memory"); }
__device__ __forceinline__ void wg_commit() { asm volatile("wgmma.commit_group.sync.aligned;" ::: "memory"); }
template <int N>
__device__ __forceinline__ void wg_wait() { asm volatile("wgmma.wait_group.sync.aligned %0;" ::"n"(N) : "memory"); }
template <int N>
__device__ __forceinline__ void pin(float (&r)[N]) {
#pragma unroll
  for (int i = 0; i < N; i++) asm volatile("" : "+f"(r[i])::"memory");
}
template <int N>
__device__ __forceinline__ void pin(uint32_t (&r)[N]) {
#pragma unroll
  for (int i = 0; i < N; i++) asm volatile("" : "+r"(r[i])::"memory");
}
template <int N>
__device__ __forceinline__ void zero(float (&r)[N]) {
#pragma unroll
  for (int i = 0; i < N; i++) r[i] = 0.f;
}
__device__ __forceinline__ uint64_t mkdesc(uint32_t addr, uint32_t lbo, uint32_t sbo, uint32_t sw) {
  return (uint64_t)((addr & 0x3FFFF) >> 4) | ((uint64_t)(lbo >> 4) << 16) | ((uint64_t)(sbo >> 4) << 32) | ((uint64_t)sw << 62);
}
__device__ __forceinline__ uint32_t pack_bf16(float lo, float hi) {
  uint32_t r;
  asm("cvt.rn.bf16x2.f32 %0, %1, %2;" : "=r"(r) : "f"(hi), "f"(lo));
  return r;
}
__device__ __forceinline__ uint32_t pack_f16(float lo, float hi) {
  uint32_t r;
  asm("cvt.rn.f16x2.f32 %0, %1, %2;" : "=r"(r) : "f"(hi), "f"(lo));
  return r;
}
__device__ __forceinline__ uint32_t mul_bf16(uint32_t a, uint32_t b) {
  uint32_t r;
  asm("fma.rn.bf16x2 %0, %1, %2, %3;" : "=r"(r) : "r"(a), "r"(b), "r"(0x80008000u));
  return r;
}
__device__ __forceinline__ float bf_lo(uint32_t u) { return __uint_as_float(u << 16); }
__device__ __forceinline__ float bf_hi(uint32_t u) { return __uint_as_float(u & 0xffff0000u); }
__device__ __forceinline__ float ex2(float x) {
  float r;
  asm("ex2.approx.ftz.f32 %0, %1;" : "=f"(r) : "f"(x));
  return r;
}
__device__ __forceinline__ float rcp(float x) {
  float r;
  asm("rcp.approx.ftz.f32 %0, %1;" : "=f"(r) : "f"(x));
  return r;
}
__device__ __forceinline__ float pow2f(int e) { return __uint_as_float((uint32_t)(e + 127) << 23); }
__device__ __forceinline__ void stsm4(uint32_t a, uint32_t r0, uint32_t r1, uint32_t r2, uint32_t r3) {
  asm volatile("stmatrix.sync.aligned.m8n8.x4.shared.b16 [%0], {%1,%2,%3,%4};" ::"r"(a), "r"(r0), "r"(r1), "r"(r2), "r"(r3)
               : "memory");
}
__device__ __forceinline__ void stsm2(uint32_t a, uint32_t r0, uint32_t r1) {
  asm volatile("stmatrix.sync.aligned.m8n8.x2.shared.b16 [%0], {%1,%2};" ::"r"(a), "r"(r0), "r"(r1) : "memory");
}
__device__ __forceinline__ void ldsm4(uint32_t a, uint32_t& r0, uint32_t& r1, uint32_t& r2, uint32_t& r3) {
  asm volatile("ldmatrix.sync.aligned.m8n8.x4.shared.b16 {%0,%1,%2,%3}, [%4];"
               : "=r"(r0), "=r"(r1), "=r"(r2), "=r"(r3)
               : "r"(a)
               : "memory");
}
__device__ __forceinline__ float qsum(float v) {
  v += __shfl_xor_sync(~0u, v, 1);
  return v + __shfl_xor_sync(~0u, v, 2);
}
__device__ __forceinline__ float qmax(float v) {
  v = fmaxf(v, __shfl_xor_sync(~0u, v, 1));
  return fmaxf(v, __shfl_xor_sync(~0u, v, 2));
}
__device__ __forceinline__ void wait_count(const unsigned* p, unsigned target) {
  unsigned v, it = 0;
  do {
    asm volatile("ld.acquire.gpu.global.u32 %0, [%1];" : "=r"(v) : "l"(p) : "memory");
  } while ((int)(v - target) < 0 && ++it < (SPIN_LIMIT >> 3));
}
__device__ __forceinline__ void publish(unsigned* p) {
  asm volatile("red.relaxed.gpu.global.add.u32 [%0], 1;" ::"l"(p) : "memory");
}
__device__ __forceinline__ int act_index(int g16, int kb, int lane) {
  return (((g16 >> 2) * 10 + (kb >> 3)) * 32 + (g16 & 3) * 8 + (kb & 7)) * 64 + ((lane & 2) << 3) + ((lane >> 2) << 1) + (lane & 1);
}

__device__ __forceinline__ void mma_rs192_bf16_t(float (&d)[96], uint32_t a0, uint32_t a1, uint32_t a2, uint32_t a3, uint64_t db, int acc) {
  asm volatile("{.reg .pred p; setp.ne.b32 p,%101,0;\n"
    "wgmma.mma_async.sync.aligned.m64n192k16.f32.bf16.bf16 "
    "{%0,%1,%2,%3,%4,%5,%6,%7,%8,%9,%10,%11,%12,%13,%14,%15,%16,%17,%18,%19,%20,%21,%22,%23,%24,%25,%26,%27,%28,%29"
    ",%30,%31,%32,%33,%34,%35,%36,%37,%38,%39,%40,%41,%42,%43,%44,%45,%46,%47,%48,%49,%50,%51,%52,%53,%54,%55,%56,%"
    "57,%58,%59,%60,%61,%62,%63,%64,%65,%66,%67,%68,%69,%70,%71,%72,%73,%74,%75,%76,%77,%78,%79,%80,%81,%82,%83,%84"
    ",%85,%86,%87,%88,%89,%90,%91,%92,%93,%94,%95},{%96,%97,%98,%99},%100,p,1,1,1;"
    "}\n"
    : "+f"(d[0]), "+f"(d[1]), "+f"(d[2]), "+f"(d[3]), "+f"(d[4]), "+f"(d[5]), "+f"(d[6]), "+f"(d[7]),
      "+f"(d[8]), "+f"(d[9]), "+f"(d[10]), "+f"(d[11]), "+f"(d[12]), "+f"(d[13]), "+f"(d[14]), "+f"(d[15]),
      "+f"(d[16]), "+f"(d[17]), "+f"(d[18]), "+f"(d[19]), "+f"(d[20]), "+f"(d[21]), "+f"(d[22]), "+f"(d[23]),
      "+f"(d[24]), "+f"(d[25]), "+f"(d[26]), "+f"(d[27]), "+f"(d[28]), "+f"(d[29]), "+f"(d[30]), "+f"(d[31]),
      "+f"(d[32]), "+f"(d[33]), "+f"(d[34]), "+f"(d[35]), "+f"(d[36]), "+f"(d[37]), "+f"(d[38]), "+f"(d[39]),
      "+f"(d[40]), "+f"(d[41]), "+f"(d[42]), "+f"(d[43]), "+f"(d[44]), "+f"(d[45]), "+f"(d[46]), "+f"(d[47]),
      "+f"(d[48]), "+f"(d[49]), "+f"(d[50]), "+f"(d[51]), "+f"(d[52]), "+f"(d[53]), "+f"(d[54]), "+f"(d[55]),
      "+f"(d[56]), "+f"(d[57]), "+f"(d[58]), "+f"(d[59]), "+f"(d[60]), "+f"(d[61]), "+f"(d[62]), "+f"(d[63]),
      "+f"(d[64]), "+f"(d[65]), "+f"(d[66]), "+f"(d[67]), "+f"(d[68]), "+f"(d[69]), "+f"(d[70]), "+f"(d[71]),
      "+f"(d[72]), "+f"(d[73]), "+f"(d[74]), "+f"(d[75]), "+f"(d[76]), "+f"(d[77]), "+f"(d[78]), "+f"(d[79]),
      "+f"(d[80]), "+f"(d[81]), "+f"(d[82]), "+f"(d[83]), "+f"(d[84]), "+f"(d[85]), "+f"(d[86]), "+f"(d[87]),
      "+f"(d[88]), "+f"(d[89]), "+f"(d[90]), "+f"(d[91]), "+f"(d[92]), "+f"(d[93]), "+f"(d[94]), "+f"(d[95])
    : "r"(a0), "r"(a1), "r"(a2), "r"(a3), "l"(db), "r"(acc));
}
__device__ __forceinline__ void mma_rs48_bf16_t(float (&d)[24], uint32_t a0, uint32_t a1, uint32_t a2, uint32_t a3, uint64_t db, int acc) {
  asm volatile("{.reg .pred p; setp.ne.b32 p,%29,0;\n"
    "wgmma.mma_async.sync.aligned.m64n48k16.f32.bf16.bf16 "
    "{%0,%1,%2,%3,%4,%5,%6,%7,%8,%9,%10,%11,%12,%13,%14,%15,%16,%17,%18,%19,%20,%21,%22,%23},{%24,%25,%26,%27},%28,"
    "p,1,1,1;"
    "}\n"
    : "+f"(d[0]), "+f"(d[1]), "+f"(d[2]), "+f"(d[3]), "+f"(d[4]), "+f"(d[5]), "+f"(d[6]), "+f"(d[7]),
      "+f"(d[8]), "+f"(d[9]), "+f"(d[10]), "+f"(d[11]), "+f"(d[12]), "+f"(d[13]), "+f"(d[14]), "+f"(d[15]),
      "+f"(d[16]), "+f"(d[17]), "+f"(d[18]), "+f"(d[19]), "+f"(d[20]), "+f"(d[21]), "+f"(d[22]), "+f"(d[23])
    : "r"(a0), "r"(a1), "r"(a2), "r"(a3), "l"(db), "r"(acc));
}
__device__ __forceinline__ void mma_rs40_bf16(float (&d)[20], uint32_t a0, uint32_t a1, uint32_t a2, uint32_t a3, uint64_t db, int acc) {
  asm volatile("{.reg .pred p; setp.ne.b32 p,%25,0;\n"
    "wgmma.mma_async.sync.aligned.m64n40k16.f32.bf16.bf16 "
    "{%0,%1,%2,%3,%4,%5,%6,%7,%8,%9,%10,%11,%12,%13,%14,%15,%16,%17,%18,%19},{%20,%21,%22,%23},%24,p,1,1,0;"
    "}\n"
    : "+f"(d[0]), "+f"(d[1]), "+f"(d[2]), "+f"(d[3]), "+f"(d[4]), "+f"(d[5]), "+f"(d[6]), "+f"(d[7]),
      "+f"(d[8]), "+f"(d[9]), "+f"(d[10]), "+f"(d[11]), "+f"(d[12]), "+f"(d[13]), "+f"(d[14]), "+f"(d[15]),
      "+f"(d[16]), "+f"(d[17]), "+f"(d[18]), "+f"(d[19])
    : "r"(a0), "r"(a1), "r"(a2), "r"(a3), "l"(db), "r"(acc));
}
__device__ __forceinline__ void mma_ss32_bf16_tt(float (&d)[16], uint64_t da, uint64_t db, int acc) {
  asm volatile("{.reg .pred p; setp.ne.b32 p,%18,0;\n"
    "wgmma.mma_async.sync.aligned.m64n32k16.f32.bf16.bf16 "
    "{%0,%1,%2,%3,%4,%5,%6,%7,%8,%9,%10,%11,%12,%13,%14,%15},%16,%17,p,1,1,1,1;"
    "}\n"
    : "+f"(d[0]), "+f"(d[1]), "+f"(d[2]), "+f"(d[3]), "+f"(d[4]), "+f"(d[5]), "+f"(d[6]), "+f"(d[7]),
      "+f"(d[8]), "+f"(d[9]), "+f"(d[10]), "+f"(d[11]), "+f"(d[12]), "+f"(d[13]), "+f"(d[14]), "+f"(d[15])
    : "l"(da), "l"(db), "r"(acc));
}
__device__ __forceinline__ void mma_rs64_bf16(float (&d)[32], uint32_t a0, uint32_t a1, uint32_t a2, uint32_t a3, uint64_t db, int acc) {
  asm volatile("{.reg .pred p; setp.ne.b32 p,%37,0;\n"
    "wgmma.mma_async.sync.aligned.m64n64k16.f32.bf16.bf16 "
    "{%0,%1,%2,%3,%4,%5,%6,%7,%8,%9,%10,%11,%12,%13,%14,%15,%16,%17,%18,%19,%20,%21,%22,%23,%24,%25,%26,%27,%28,%29"
    ",%30,%31},{%32,%33,%34,%35},%36,p,1,1,0;"
    "}\n"
    : "+f"(d[0]), "+f"(d[1]), "+f"(d[2]), "+f"(d[3]), "+f"(d[4]), "+f"(d[5]), "+f"(d[6]), "+f"(d[7]),
      "+f"(d[8]), "+f"(d[9]), "+f"(d[10]), "+f"(d[11]), "+f"(d[12]), "+f"(d[13]), "+f"(d[14]), "+f"(d[15]),
      "+f"(d[16]), "+f"(d[17]), "+f"(d[18]), "+f"(d[19]), "+f"(d[20]), "+f"(d[21]), "+f"(d[22]), "+f"(d[23]),
      "+f"(d[24]), "+f"(d[25]), "+f"(d[26]), "+f"(d[27]), "+f"(d[28]), "+f"(d[29]), "+f"(d[30]), "+f"(d[31])
    : "r"(a0), "r"(a1), "r"(a2), "r"(a3), "l"(db), "r"(acc));
}
__device__ __forceinline__ void mma_rs24_f16_t(float (&d)[12], uint32_t a0, uint32_t a1, uint32_t a2, uint32_t a3, uint64_t db, int acc) {
  asm volatile("{.reg .pred p; setp.ne.b32 p,%17,0;\n"
    "wgmma.mma_async.sync.aligned.m64n24k16.f32.f16.f16 "
    "{%0,%1,%2,%3,%4,%5,%6,%7,%8,%9,%10,%11},{%12,%13,%14,%15},%16,p,1,1,1;"
    "}\n"
    : "+f"(d[0]), "+f"(d[1]), "+f"(d[2]), "+f"(d[3]), "+f"(d[4]), "+f"(d[5]), "+f"(d[6]), "+f"(d[7]),
      "+f"(d[8]), "+f"(d[9]), "+f"(d[10]), "+f"(d[11])
    : "r"(a0), "r"(a1), "r"(a2), "r"(a3), "l"(db), "r"(acc));
}
__device__ __forceinline__ void mma_rs24_bf16_t(float (&d)[12], uint32_t a0, uint32_t a1, uint32_t a2, uint32_t a3, uint64_t db, int acc) {
  asm volatile("{.reg .pred p; setp.ne.b32 p,%17,0;\n"
    "wgmma.mma_async.sync.aligned.m64n24k16.f32.bf16.bf16 "
    "{%0,%1,%2,%3,%4,%5,%6,%7,%8,%9,%10,%11},{%12,%13,%14,%15},%16,p,1,1,1;"
    "}\n"
    : "+f"(d[0]), "+f"(d[1]), "+f"(d[2]), "+f"(d[3]), "+f"(d[4]), "+f"(d[5]), "+f"(d[6]), "+f"(d[7]),
      "+f"(d[8]), "+f"(d[9]), "+f"(d[10]), "+f"(d[11])
    : "r"(a0), "r"(a1), "r"(a2), "r"(a3), "l"(db), "r"(acc));
}
__device__ __forceinline__ void mma_rs96_bf16_t(float (&d)[48], uint32_t a0, uint32_t a1, uint32_t a2, uint32_t a3, uint64_t db, int acc) {
  asm volatile("{.reg .pred p; setp.ne.b32 p,%53,0;\n"
    "wgmma.mma_async.sync.aligned.m64n96k16.f32.bf16.bf16 "
    "{%0,%1,%2,%3,%4,%5,%6,%7,%8,%9,%10,%11,%12,%13,%14,%15,%16,%17,%18,%19,%20,%21,%22,%23,%24,%25,%26,%27,%28,%29"
    ",%30,%31,%32,%33,%34,%35,%36,%37,%38,%39,%40,%41,%42,%43,%44,%45,%46,%47},{%48,%49,%50,%51},%52,p,1,1,1;"
    "}\n"
    : "+f"(d[0]), "+f"(d[1]), "+f"(d[2]), "+f"(d[3]), "+f"(d[4]), "+f"(d[5]), "+f"(d[6]), "+f"(d[7]),
      "+f"(d[8]), "+f"(d[9]), "+f"(d[10]), "+f"(d[11]), "+f"(d[12]), "+f"(d[13]), "+f"(d[14]), "+f"(d[15]),
      "+f"(d[16]), "+f"(d[17]), "+f"(d[18]), "+f"(d[19]), "+f"(d[20]), "+f"(d[21]), "+f"(d[22]), "+f"(d[23]),
      "+f"(d[24]), "+f"(d[25]), "+f"(d[26]), "+f"(d[27]), "+f"(d[28]), "+f"(d[29]), "+f"(d[30]), "+f"(d[31]),
      "+f"(d[32]), "+f"(d[33]), "+f"(d[34]), "+f"(d[35]), "+f"(d[36]), "+f"(d[37]), "+f"(d[38]), "+f"(d[39]),
      "+f"(d[40]), "+f"(d[41]), "+f"(d[42]), "+f"(d[43]), "+f"(d[44]), "+f"(d[45]), "+f"(d[46]), "+f"(d[47])
    : "r"(a0), "r"(a1), "r"(a2), "r"(a3), "l"(db), "r"(acc));
}
__device__ __forceinline__ void mma_rs64_bf16_t(float (&d)[32], uint32_t a0, uint32_t a1, uint32_t a2, uint32_t a3, uint64_t db, int acc) {
  asm volatile("{.reg .pred p; setp.ne.b32 p,%37,0;\n"
    "wgmma.mma_async.sync.aligned.m64n64k16.f32.bf16.bf16 "
    "{%0,%1,%2,%3,%4,%5,%6,%7,%8,%9,%10,%11,%12,%13,%14,%15,%16,%17,%18,%19,%20,%21,%22,%23,%24,%25,%26,%27,%28,%29"
    ",%30,%31},{%32,%33,%34,%35},%36,p,1,1,1;"
    "}\n"
    : "+f"(d[0]), "+f"(d[1]), "+f"(d[2]), "+f"(d[3]), "+f"(d[4]), "+f"(d[5]), "+f"(d[6]), "+f"(d[7]),
      "+f"(d[8]), "+f"(d[9]), "+f"(d[10]), "+f"(d[11]), "+f"(d[12]), "+f"(d[13]), "+f"(d[14]), "+f"(d[15]),
      "+f"(d[16]), "+f"(d[17]), "+f"(d[18]), "+f"(d[19]), "+f"(d[20]), "+f"(d[21]), "+f"(d[22]), "+f"(d[23]),
      "+f"(d[24]), "+f"(d[25]), "+f"(d[26]), "+f"(d[27]), "+f"(d[28]), "+f"(d[29]), "+f"(d[30]), "+f"(d[31])
    : "r"(a0), "r"(a1), "r"(a2), "r"(a3), "l"(db), "r"(acc));
}

namespace k1 {
constexpr int XR = 3, WR = 3;
constexpr uint32_t X_OFF = 0, X_SLOT = 16384;
constexpr uint32_t W_OFF = X_OFF + XR * X_SLOT;
constexpr uint32_t W_HALF = 15360, W_SLOT = 2 * W_HALF;
constexpr uint32_t STG_OFF = W_OFF + WR * W_SLOT;
constexpr uint32_t TG = 33 * 128;
constexpr uint32_t WPHI_OFF = STG_OFF + 16 * TG;
constexpr uint32_t BAR_OFF = WPHI_OFF + 2 * 3840;
constexpr uint32_t SMEM = BAR_OFF + 256 + 1024;
constexpr uint32_t B_XF = 0, B_XE = 8 * XR, B_WF = 16 * XR, B_WE = B_WF + 8 * WR, B_RDY = B_WE + 8 * WR, B_PUB = B_RDY + 8,
                   B_KV = B_PUB + 8;
struct Maps { CUtensorMap x, w1[2], w2[2], r1[2], r2[2]; };
}

#define ACC(p, j, i) ((j) < 8 ? am[(8 * (p) + ((j) & 7)) * 4 + (i)] : ar[(2 * (p) + ((j) & 1)) * 4 + (i)])

__device__ __forceinline__ void hedgehog(const float (&d)[20], uint32_t (&F)[2][10]) {
  float mx[4], mn[4], sp[4], sn[4];
#define HX(r, i) d[((r) >> 1 ? ((i) < 4 ? 12 + 4 * ((i) >> 1) + ((i) & 1) : 9) : ((i) < 4 ? 4 * ((i) >> 1) + ((i) & 1) : 8)) + 2 * ((r) & 1)]
#pragma unroll
  for (int r = 0; r < 4; r++) {
    mx[r] = fmaxf(fmaxf(fmaxf(HX(r, 0), HX(r, 1)), fmaxf(HX(r, 2), HX(r, 3))), HX(r, 4));
    mn[r] = fminf(fminf(fminf(HX(r, 0), HX(r, 1)), fminf(HX(r, 2), HX(r, 3))), HX(r, 4));
  }
#pragma unroll
  for (int o = 1; o < 4; o <<= 1)
#pragma unroll
    for (int r = 0; r < 4; r++) {
      mx[r] = fmaxf(mx[r], __shfl_xor_sync(~0u, mx[r], o));
      mn[r] = fminf(mn[r], __shfl_xor_sync(~0u, mn[r], o));
    }
#pragma unroll
  for (int r = 0; r < 4; r++) {
    const float a = -mx[r] * L2E, b = mn[r] * L2E;
    float p[5], n[5];
#pragma unroll
    for (int i = 0; i < 5; i++) {
      p[i] = ex2(fmaf(HX(r, i), L2E, a));
      n[i] = ex2(fmaf(HX(r, i), -L2E, b));
    }
    sp[r] = (p[0] + p[1]) + (p[2] + p[3]) + p[4];
    sn[r] = (n[0] + n[1]) + (n[2] + n[3]) + n[4];
    uint32_t* f = F[r >> 1] + (r & 1);
    f[0] = pack_bf16(p[0], p[1]); f[2] = pack_bf16(p[2], p[3]);
    f[4] = pack_bf16(n[0], n[1]); f[6] = pack_bf16(n[2], n[3]);
    f[8] = pack_bf16(p[4], n[4]);
  }
#undef HX
#pragma unroll
  for (int o = 1; o < 4; o <<= 1)
#pragma unroll
    for (int r = 0; r < 4; r++) {
      sp[r] += __shfl_xor_sync(~0u, sp[r], o);
      sn[r] += __shfl_xor_sync(~0u, sn[r], o);
    }
#pragma unroll
  for (int r = 0; r < 4; r++) {
    const uint32_t rr = pack_bf16(rcp(sp[r]), rcp(sn[r])), rp = __byte_perm(rr, 0, 0x1010), rn = __byte_perm(rr, 0, 0x3232);
    uint32_t* f = F[r >> 1] + (r & 1);
    f[0] = mul_bf16(f[0], rp); f[2] = mul_bf16(f[2], rp);
    f[4] = mul_bf16(f[4], rn); f[6] = mul_bf16(f[6], rn);
    f[8] = mul_bf16(f[8], rr);
  }
}

__global__ void __cluster_dims__(2, 1, 1) __launch_bounds__(384, 1)
k_qkv(const __grid_constant__ k1::Maps maps, const __nv_bfloat16* __restrict__ x, const __nv_bfloat16* __restrict__ wphi,
      const __nv_bfloat16* __restrict__ gate_w) {
  using namespace k1;
  extern __shared__ unsigned char smem_raw[];
  const uint32_t sb = (smem_u32(smem_raw) + 1023) & ~1023u;
  const uint32_t bars = sb + BAR_OFF;
  const int tid = threadIdx.x, lane = tid & 31, warp = __shfl_sync(~0u, tid >> 5, 0);
  const uint32_t rank = blockIdx.x & 1;
  const int cid = blockIdx.x >> 1, grp = cid & 7, rb = (cid >> 3) * 2 + rank;
  const int c = lane & 3;
  if (blockIdx.x >= 128) {
    asm volatile("griddepcontrol.launch_dependents;" ::: "memory");
    uint32_t gv[10];
#pragma unroll
    for (int j = 0; j < 10; j++) gv[j] = __ldg((const uint32_t*)gate_w + j * 32 + lane);
#pragma unroll 2
    for (int r = (blockIdx.x - 128) * 256 + warp; r < (blockIdx.x - 127) * 256; r += 12) {
      uint32_t xv[2][10];
#pragma unroll
      for (int j = 0; j < 10; j++) {
        xv[0][j] = __ldg((const uint32_t*)x + r * 640 + j * 32 + lane);
        xv[1][j] = __ldg((const uint32_t*)x + r * 640 + 320 + j * 32 + lane);
      }
      float t0 = 0.f, t1 = 0.f;
#pragma unroll
      for (int j = 0; j < 10; j++) {
        t0 = fmaf(bf_lo(xv[0][j]), bf_lo(gv[j]), fmaf(bf_hi(xv[0][j]), bf_hi(gv[j]), t0));
        t1 = fmaf(bf_lo(xv[1][j]), bf_lo(gv[j]), fmaf(bf_hi(xv[1][j]), bf_hi(gv[j]), t1));
      }
      float t = (lane & 1 ? t1 : t0) + __shfl_xor_sync(~0u, lane & 1 ? t0 : t1, 1);
#pragma unroll
      for (int o = 16; o > 1; o >>= 1) t += __shfl_xor_sync(~0u, t, o);
      if (lane < 2) g_gate[2 * r + lane] = __fdividef(1.f, 1.f + __expf(-t));
    }
    return;
  }

  auto load_x = [&](int kt) {
    const int s = kt % XR;
    mbar_expect(bars + B_XF + 8 * s, X_SLOT);
    tma2(sb + X_OFF + s * X_SLOT, &maps.x, kt * 64, rb * 128, bars + B_XF + 8 * s);
  };
  auto load_w = [&](int it) {
    const int s = it % WR, p = it >= 10, k = (p ? 19 - it : it) * 64 + rank * 32;
    const uint32_t dst = sb + W_OFF + s * W_SLOT + rank * W_HALF, bar = bars + B_WF + 8 * s;
    mbar_expect(bar, W_SLOT);
    tma3_mc(dst + 4096, &maps.w2[1 - p], grp * 80, k, 1, bar);
    tma3_mc(dst, &maps.w1[p], grp * 80, k, 0, bar);
    tma3_mc(dst + 13312, &maps.r2[1 - p], grp * 80 + 64, k, 1, bar);
    tma3_mc(dst + 12288, &maps.r1[p], grp * 80 + 64, k, 0, bar);
  };
  if (tid == 256) {
    TS(0, 0);
    for (int i = 0; i < XR; i++) { mbar_init(bars + B_XF + 8 * i, 1); mbar_init(bars + B_XE + 8 * i, 8); }
    for (int i = 0; i < WR; i++) { mbar_init(bars + B_WF + 8 * i, 1); mbar_init(bars + B_WE + 8 * i, 16); }
    mbar_init(bars + B_RDY, 97);
    mbar_init(bars + B_PUB, 256);
    mbar_init(bars + B_KV, 96);
    asm volatile("fence.mbarrier_init.release.cluster;" ::: "memory");
  }
  if (tid >= 288 && tid < 297) prefetch_map(&maps.x + (tid - 288));
  __syncwarp();
  cluster_arrive();
  if (tid == 256) load_x(0);
  asm volatile("griddepcontrol.launch_dependents;" ::: "memory");
  __syncwarp();
  cluster_wait();

  if (warp >= 8) {
    asm volatile("setmaxnreg.dec.sync.aligned.u32 40;");
    if (warp == 8) {
      if (lane == 0) {
        uint32_t xph = 0, wph = 0;
#pragma unroll 1
        for (int n = 0; n < 20; n++) {
          if (n && (n < 10 || n >= 10 + XR)) {
            const int kn = n < 10 ? n : 19 - n, t = kn % XR;
            if (n >= XR) {
              mbar_wait(bars + B_XE + 8 * t, (xph >> t) & 1);
              xph ^= 1u << t;
            }
            load_x(kn);
          }
          if (n >= WR) {
            const int s = n % WR;
            mbar_wait(bars + B_WE + 8 * s, (wph >> s) & 1);
            wph ^= 1u << s;
          }
          load_w(n);
        }
      }
    } else {
      const int ht = tid - 288;
      unsigned char* sp = smem_raw + (sb - smem_u32(smem_raw));
      mbar_wait_long(bars + B_WF, 0);
      unsigned epoch = 0;
      if (ht == 0) asm volatile("ld.relaxed.gpu.global.u32 %0, [%1];" : "=r"(epoch) : "l"(g_sync + 8 + grp) : "memory");
      if (blockIdx.x == 0 && ht < 32) g_cnt[ht] = 0;
      if (ht < 60) g_kvs[grp * 960 + rb * 60 + ht] = make_float4(0.f, 0.f, 0.f, 0.f);
      const int wj = ht / 20, wk = ht % 20 + 20 * (wj & 1);
      uint32_t wv[10];
#pragma unroll
      for (int i = 0; i < 10; i++) wv[i] = ht < 80 ? __ldg((const uint32_t*)wphi + grp * 800 + ht * 10 + i) : 0u;
#pragma unroll
      for (int i = 0; i < 5; i++) *(uint4*)(sp + WPHI_OFF + (i * 96 + ht) * 16) = make_uint4(0u, 0u, 0u, 0u);
#pragma unroll
      for (int i = 0; i < 4; i++)
        *(uint4*)(sp + STG_OFF + (4 * i + (ht >> 3) / 3) * TG + (20 + 6 * ((ht >> 3) % 3)) * 128 + (ht & 7) * 16) = make_uint4(0x3f80u, 0u, 0u, 0u);
      epoch += 16;
      bar_sync(1, 96);
      if (ht < 80) {
        unsigned char* q = sp + WPHI_OFF + (wj >> 1) * 3840 + (wk >> 3) * 128 + (wk & 7) * 2;
#pragma unroll
        for (int i = 0; i < 10; i++) {
          unsigned char* t = q + (i < 8 ? (i >> 2) * 768 + (i & 3) * 32 + (wj & 1) * 2304 : 1536 + (i - 8) * 64 + (wj & 1) * 16);
          *(uint16_t*)t = (uint16_t)wv[i];
          *(uint16_t*)(t + (i < 8 ? 16 : 32)) = (uint16_t)(wv[i] >> 16);
        }
      }
      fence_async();
      mbar_arrive(bars + B_RDY);
      if (ht == 0) {
        asm volatile("fence.acq_rel.gpu;" ::: "memory");
        publish(g_sync + grp);
        wait_count(g_sync + grp, epoch);
        mbar_arrive(bars + B_RDY);
        TS(0, 8);
        mbar_wait_long(bars + B_PUB, 0);
        for (int i = 0; i < 6; i++)
          asm volatile("cp.reduce.async.bulk.global.shared::cta.bulk_group.add.f32 [%0], [%1], 2560;" ::"l"(g_kvs + grp * 960 + i * 160),
                       "r"(sb + STG_OFF + i * TG)
                       : "memory");
        asm volatile("cp.async.bulk.commit_group;" ::: "memory");
        asm volatile("cp.async.bulk.wait_group 0;" ::: "memory");
        asm volatile("fence.proxy.async.global;" ::: "memory");
        asm volatile("fence.acq_rel.gpu;" ::: "memory");
        publish(g_sync + 8 + grp);
        TS(0, 10);
        wait_count(g_sync + 8 + grp, epoch);
        TS(0, 13);
      }
      bar_sync(1, 96);
      const int s0 = ht / 6, n = (ht % 6) * 4;
#pragma unroll
      for (int k = 0; k < 3; k++) {
        float4 t[4];
        if (k < 2 || ht < 48) {
#pragma unroll
          for (int j = 0; j < 4; j++) t[j] = __ldcg(g_kvs + grp * 960 + j * 240 + k * 96 + ht);
#pragma unroll
          for (int j = 0; j < 4; j++)
            *(uint2*)(sp + STG_OFF + (2 * k + (s0 >> 3)) * TG + (20 + 3 * j + (n >> 3)) * 128 + (s0 & 7) * 16 + (n & 7) * 2) =
                make_uint2(pack_bf16(t[j].x, t[j].y), pack_bf16(t[j].z, t[j].w));
        }
      }
      *(uint4*)(sp + STG_OFF + 5 * TG + 20 * 128 + ht * 16) = make_uint4(0u, 0u, 0u, 0u);
      fence_async();
      mbar_arrive(bars + B_KV);
      if (ht == 0) TS(0, 12);
    }
  } else {
    asm volatile("setmaxnreg.inc.sync.aligned.u32 232;");
    const int wg = warp >> 2, w = warp & 3;
    if (tid == 0) TS(0, 1);
    float am[96], ar[24];
    zero(am); zero(ar);
    const int xrow = wg * 64 + w * 16 + (lane & 15), g16 = rb * 8 + wg * 4 + w;
    const uint32_t xaddr = sb + X_OFF + xrow * 128, xc = (lane >> 4) ^ (xrow & 7);
    const uint32_t srow = (lane & 7) * 16, mh = (lane >> 3) & 1, mb = lane >> 4;
    uint32_t xph = 0, wph = 0;
    const uint64_t dm0 = mkdesc(sb + W_OFF, 4096, 1024, 1), dr0 = mkdesc(sb + W_OFF + 12288, 1024, 256, 3);
    const uint64_t dphi = mkdesc(sb + WPHI_OFF, 128, 768, 0), dt = mkdesc(sb + STG_OFF, TG, 128, 0);
    auto load_a = [&](uint32_t(&a)[8], int xs, int half) {
      ldsm4(xaddr + xs * X_SLOT + ((xc ^ (4 * half)) << 4), a[0], a[1], a[2], a[3]);
      ldsm4(xaddr + xs * X_SLOT + ((xc ^ (4 * half + 2)) << 4), a[4], a[5], a[6], a[7]);
    };
    auto mma_half = [&](const uint32_t(&a)[8], uint64_t dm, uint64_t dr, int acc) {
      wg_fence();
      mma_rs48_bf16_t(ar, a[0], a[1], a[2], a[3], dr, acc);
      mma_rs192_bf16_t(am, a[0], a[1], a[2], a[3], dm, acc);
      mma_rs48_bf16_t(ar, a[4], a[5], a[6], a[7], dr + 32, 1);
      mma_rs192_bf16_t(am, a[4], a[5], a[6], a[7], dm + 128, 1);
      wg_commit();
    };
    auto gemm = [&](const int pass) {
      uint32_t a0[8], a1[8];
      int xs = pass ? 9 % XR : 0, ws = pass ? 10 % WR : 0;
      if (pass == 0) { mbar_wait(bars + B_XF, 0); xph = 1; }
      load_a(a0, xs, 0);
      pin(am); pin(ar);
#pragma unroll 1
      for (int i = 0; i < 10; i++) {
        const int it = pass * 10 + i, kt = pass ? 9 - i : i;
        const uint32_t prev = bars + B_WE + 8 * (ws ? ws - 1 : WR - 1);
        const uint64_t dm = dm0 + ws * (W_SLOT >> 4), dr = dr0 + ws * (W_SLOT >> 4);
        bool rel = i > 0 && it <= 20 - WR;
        if (!mbar_test(bars + B_WF + 8 * ws, (wph >> ws) & 1)) {
          wg_wait<0>();
          if (rel && lane < 2) mbar_arrive_cta(prev, lane);
          rel = false;
          mbar_wait(bars + B_WF + 8 * ws, (wph >> ws) & 1);
        }
        wph ^= 1u << ws;
        if (tid == 0 && it == 0) TS(0, 2);
        mma_half(a0, dm, dr, i);
        wg_wait<1>(); pin(a1);
        load_a(a1, xs, 1);
        if (rel && lane < 2) mbar_arrive_cta(prev, lane);
        mma_half(a1, dm + (W_HALF >> 4), dr + (W_HALF >> 4), 1);
        if (lane == 0 && (pass ? kt >= XR : kt < 10 - XR)) mbar_arrive(bars + B_XE + 8 * xs);
        ws = ws == WR - 1 ? 0 : ws + 1;
        if (i < 9) {
          xs = pass ? (xs ? xs - 1 : XR - 1) : (xs == XR - 1 ? 0 : xs + 1);
          if (pass == 0 || i + 1 >= XR) {
            mbar_wait(bars + B_XF + 8 * xs, (xph >> xs) & 1);
            xph ^= 1u << xs;
          }
        }
        wg_wait<1>(); pin(a0);
        load_a(a0, xs, 0);
      }
      wg_wait<0>();
      pin(am); pin(ar); pin(a0); pin(a1);
      if (pass == 0 && lane < 2) mbar_arrive_cta(bars + B_WE + 8 * (9 % WR), lane);
      if (tid == 0) TS(0, 3 + 2 * pass);
    };
    float d[2][20];
    uint32_t pk[24];
    auto chains = [&](const int part) {
#pragma unroll
      for (int j = 0; j < 12; j++) {
        const int b = 5 * (j / 6) + j % 6;
        pk[2 * j] = j % 6 < 5 ? pack_bf16(ACC(part, b < 10 ? b : 0, 0), ACC(part, b < 10 ? b : 0, 1)) : 0u;
        pk[2 * j + 1] = j % 6 < 5 ? pack_bf16(ACC(part, b < 10 ? b : 0, 2), ACC(part, b < 10 ? b : 0, 3)) : 0u;
      }
      zero(d[0]); zero(d[1]); pin(d[0]); pin(d[1]); pin(pk);
      wg_fence();
#pragma unroll
      for (int s = 0; s < 3; s++)
#pragma unroll
        for (int p = 0; p < 2; p++)
          mma_rs40_bf16(d[p], pk[12 * p + 4 * s], pk[12 * p + 4 * s + 1], pk[12 * p + 4 * s + 2], pk[12 * p + 4 * s + 3], dphi + p * 240 + s * 16, s);
      wg_commit();
    };

    gemm(0);
    {
      mbar_wait(bars + B_RDY, 0);
      chains(1);
      const uint32_t trow = sb + STG_OFF + (8 * wg + 2 * w + mh) * TG + srow;
#pragma unroll
      for (int j = 0; j < 10; j += 2)
        stsm4(trow + (mb ? 22 + j + (j + 1 >= 5) : 21 + j + (j >= 5)) * 128, pack_bf16(ACC(2, j, 0), ACC(2, j, 1)),
              pack_bf16(ACC(2, j, 2), ACC(2, j, 3)), pack_bf16(ACC(2, j + 1, 0), ACC(2, j + 1, 1)), pack_bf16(ACC(2, j + 1, 2), ACC(2, j + 1, 3)));
      const float qs = 0.22360679774997896f * L2E * 8.673617379884035e-19f;
#pragma unroll
      for (int j = 0; j < 4; j++) {
        const int h = grp * 4 + j, odd = j & 1, b0 = 5 * (j >> 1) + (odd ? 3 : 0), b1 = b0 + 1, b2 = 5 * (j >> 1) + 2;
        const bool valid = odd ? c >= 2 : c < 2;
        g_q1[(h * 128 + g16) * 32 + lane] =
            make_uint4(pack_bf16(ACC(0, b0, 0) * qs, ACC(0, b0, 1) * qs), pack_bf16(ACC(0, b0, 2) * qs, ACC(0, b0, 3) * qs),
                       pack_bf16(ACC(0, b1, 0) * qs, ACC(0, b1, 1) * qs), pack_bf16(ACC(0, b1, 2) * qs, ACC(0, b1, 3) * qs));
        g_q2[(h * 128 + g16) * 32 + lane] =
            valid ? make_uint2(pack_bf16(ACC(0, b2, 0) * qs, ACC(0, b2, 1) * qs), pack_bf16(ACC(0, b2, 2) * qs, ACC(0, b2, 3) * qs))
                  : make_uint2(0u, 0u);
      }
      wg_wait<0>(); pin(d[0]); pin(d[1]); pin(pk);
#pragma unroll
      for (int p = 0; p < 2; p++) {
        uint32_t F[2][10];
        hedgehog(d[p], F);
#pragma unroll
        for (int i = 0; i < 2; i++) {
          const uint32_t a = trow + (10 * p + 5 * i) * 128;
          stsm4(a + mb * 128, F[i][0], F[i][1], F[i][2], F[i][3]);
          stsm4(a + mb * 128 + 256, F[i][4], F[i][5], F[i][6], F[i][7]);
          stsm2(a + 512, F[i][8], F[i][9]);
        }
      }
      fence_async();
      bar_sync(2, 256);
      if (tid == 0) TS(0, 15);
      float ke[16], ko[16];
      zero(ke); zero(ko); pin(ke); pin(ko);
      wg_fence();
#pragma unroll
      for (int s = 0; s < 8; s++) {
        mma_ss32_bf16_tt(ke, dt + (2 * s * TG >> 4) + (10 * wg) * 8, dt + (2 * s * TG >> 4) + (20 + 6 * wg) * 8, s);
        mma_ss32_bf16_tt(ko, dt + (2 * s * TG >> 4) + (10 * wg + 5) * 8, dt + (2 * s * TG >> 4) + (23 + 6 * wg) * 8, s);
      }
      wg_commit();
      wg_wait<0>(); pin(ke); pin(ko);
      bar_sync(2, 256);
#pragma unroll
      for (int hf = 0; hf < 2; hf++) {
        const int slot = 16 * w + 8 * hf + (lane >> 2), o = 2 * hf;
        const float ze = __shfl_sync(~0u, ke[o], lane & ~3);
        if (slot < 40) {
#pragma unroll
          for (int i = 0; i < 6; i++) {
            const int f = (2 * wg + i / 3) * 960 + slot * 24 + (i % 3) * 8 + 2 * c;
            const float(&k)[16] = i < 3 ? ke : ko;
            float a = k[4 + 4 * (i % 3) + o], b = k[5 + 4 * (i % 3) + o];
            if (i == 2 && c >= 2) { a = c == 2 ? ze : 0.f; b = 0.f; }
            if (i == 5) { a = c >= 2 ? ko[o] : (c == 0 ? a : 0.f); b = c >= 2 ? ko[1 + o] : 0.f; }
            asm volatile("st.shared.v2.f32 [%0], {%1, %2};" ::"r"(sb + STG_OFF + (f / 640) * TG + (f % 640) * 4), "f"(a), "f"(b) : "memory");
          }
        }
      }
      fence_async();
      mbar_arrive(bars + B_PUB);
      if (tid == 0) TS(0, 4);
    }
    gemm(1);
    chains(0);
    float vm = 0.f;
#pragma unroll
    for (int j = 0; j < 10; j++)
#pragma unroll
      for (int i = 0; i < 4; i++) vm = fmaxf(vm, fabsf(ACC(2, j, i)));
    const uint32_t vmb = __reduce_max_sync(~0u, __float_as_uint(vm));
    int ve = 0;
    if (vmb != 0 && (vmb < 0x3a800000u || vmb >= 0x47000000u)) ve = min(max((int)(vmb >> 23) - 127 - 8, -120), 120);
    if (ve != 0) {
      const float vs = pow2f(-ve);
#pragma unroll
      for (int i = 64; i < 96; i++) am[i] *= vs;
#pragma unroll
      for (int i = 16; i < 24; i++) ar[i] *= vs;
    }
    if (lane == 0) ((int*)g_ve)[grp * 128 + g16] = ve;
    const int tg = 8 * wg + 2 * w;
    const bool pl0 = (POLY_MASK >> tg) & 1, pl1 = (POLY_MASK >> (tg + 1)) & 1;
    const uint32_t ks0 = pl0 ? 0x18001800u : 0x5d805d80u, ks1 = pl1 ? 0x18001800u : 0x5d805d80u;
    const uint32_t kx0 = (c & 1) ? (pl0 ? 0x00003f80u : 0u) : (pl0 ? 0x3f803f80u : 0x00003f80u);
    const uint32_t kx1 = (c & 1) ? (pl1 ? 0x00003f80u : 0u) : (pl1 ? 0x3f803f80u : 0x00003f80u);
    const uint32_t vx = (c & 1) ? 0u : 0x00003c00u;
    bar_sync(2, 256);
    const uint32_t stg = sb + wg * 24576;
#pragma unroll
    for (int j = 0; j < 4; j++) {
      const int odd = j & 1, b0 = 5 * (j >> 1) + (odd ? 3 : 0), b1 = b0 + 1, b2 = 5 * (j >> 1) + 2;
      const bool valid = odd ? c >= 2 : c < 2;
      const uint32_t ka = stg + j * 6144 + (2 * w + mh) * 128 + srow, va = stg + j * 6144 + 3072 + (2 * w + mh) * 384 + srow;
      stsm4(ka + mb * 1024, mul_bf16(pack_bf16(ACC(1, b0, 0), ACC(1, b0, 1)), ks0), mul_bf16(pack_bf16(ACC(1, b0, 2), ACC(1, b0, 3)), ks1),
            mul_bf16(pack_bf16(ACC(1, b1, 0), ACC(1, b1, 1)), ks0), mul_bf16(pack_bf16(ACC(1, b1, 2), ACC(1, b1, 3)), ks1));
      stsm4(va + mb * 128, pack_f16(ACC(2, b0, 0), ACC(2, b0, 1)), pack_f16(ACC(2, b0, 2), ACC(2, b0, 3)),
            pack_f16(ACC(2, b1, 0), ACC(2, b1, 1)), pack_f16(ACC(2, b1, 2), ACC(2, b1, 3)));
      stsm4(mb ? va + 256 : ka + 2048, mul_bf16(valid ? pack_bf16(ACC(1, b2, 0), ACC(1, b2, 1)) : kx0, ks0),
            mul_bf16(valid ? pack_bf16(ACC(1, b2, 2), ACC(1, b2, 3)) : kx1, ks1), valid ? pack_f16(ACC(2, b2, 0), ACC(2, b2, 1)) : vx,
            valid ? pack_f16(ACC(2, b2, 2), ACC(2, b2, 3)) : vx);
    }
    fence_async();
    bar_sync(3 + wg, 128);
    if ((tid & 127) == 0) {
      for (int j = 0; j < 4; j++) bulk_s2g((unsigned char*)g_kv + ((grp * 4 + j) * 32 + rb * 2 + wg) * 6144, stg + j * 6144, 6144);
      asm volatile("cp.async.bulk.commit_group;" ::: "memory");
    }
    if (tid == 0) TS(0, 16);
    {
      float kn[8];
#pragma unroll
      for (int j = 0; j < 4; j++)
#pragma unroll
        for (int hf = 0; hf < 2; hf++) {
          const int odd = j & 1, b0 = 5 * (j >> 1) + (odd ? 3 : 0), b1 = b0 + 1, b2 = 5 * (j >> 1) + 2, o = 2 * hf;
          float n = ACC(1, b0, o) * ACC(1, b0, o) + ACC(1, b0, o + 1) * ACC(1, b0, o + 1) + ACC(1, b1, o) * ACC(1, b1, o) +
                    ACC(1, b1, o + 1) * ACC(1, b1, o + 1);
          if (odd ? c >= 2 : c < 2) n += ACC(1, b2, o) * ACC(1, b2, o) + ACC(1, b2, o + 1) * ACC(1, b2, o + 1);
          kn[2 * j + hf] = n;
        }
      const bool u1 = c & 1, u2 = c & 2;
      float t[4];
#pragma unroll
      for (int i = 0; i < 4; i++) {
        const float e = kn[4 * (i >> 1) + (i & 1)], o = kn[4 * (i >> 1) + 2 + (i & 1)];
        t[i] = (u1 ? o : e) + __shfl_xor_sync(~0u, u1 ? e : o, 1);
      }
      const float r0 = (u2 ? t[2] : t[0]) + __shfl_xor_sync(~0u, u2 ? t[0] : t[2], 2);
      const float r1 = (u2 ? t[3] : t[1]) + __shfl_xor_sync(~0u, u2 ? t[1] : t[3], 2);
      float m = fmaxf(r0, r1);
      m = fmaxf(m, __shfl_xor_sync(~0u, m, 4));
      m = fmaxf(m, __shfl_xor_sync(~0u, m, 8));
      m = fmaxf(m, __shfl_xor_sync(~0u, m, 16));
      if (lane < 4) ((float*)g_kn2)[(grp * 4 + c) * 128 + g16] = m;
    }
    wg_wait<0>(); pin(d[0]); pin(d[1]); pin(pk);
    uint32_t F[4][10], z[8] = {0u, 0u, 0u, 0u, 0u, 0u, 0u, 0u};
    hedgehog(d[0], *(uint32_t(*)[2][10]) & F[0]);
    hedgehog(d[1], *(uint32_t(*)[2][10]) & F[2]);
    if (tid == 0) TS(0, 17);
    mbar_wait(bars + B_KV, 0);
    float ob[4][12];
#pragma unroll
    for (int j = 0; j < 4; j++) { zero(ob[j]); pin(ob[j]); pin(F[j]); }
    pin(z);
    wg_fence();
#pragma unroll
    for (int j = 0; j < 4; j++) {
      mma_rs24_bf16_t(ob[j], F[j][0], F[j][1], F[j][2], F[j][3], dt + (20 + 3 * j) * 8, 0);
      mma_rs24_bf16_t(ob[j], F[j][4], F[j][5], F[j][6], F[j][7], dt + (2 * TG >> 4) + (20 + 3 * j) * 8, 1);
      mma_rs24_bf16_t(ob[j], F[j][8], F[j][9], z[2 * j], z[2 * j + 1], dt + (4 * TG >> 4) + (20 + 3 * j) * 8, 1);
    }
    wg_commit();
    wg_wait<0>();
#pragma unroll
    for (int j = 0; j < 4; j++) pin(ob[j]);
#pragma unroll
    for (int p = 0; p < 2; p++)
#pragma unroll
      for (int hf = 0; hf < 2; hf++) {
        const float(&oe)[12] = ob[2 * p];
        const float(&oo)[12] = ob[2 * p + 1];
        const int o = 2 * hf, kb = grp * 10 + 5 * p;
        const float se = rcp(__shfl_sync(~0u, oe[8 + o], (lane & ~3) | 2) + 1e-6f), so = rcp(__shfl_sync(~0u, oo[8 + o], lane & ~3) + 1e-6f);
        uint32_t* dst = (uint32_t*)g_act[0] + 32 * hf;
        dst[act_index(g16, kb, lane)] = pack_bf16(oe[o] * se, oe[1 + o] * se);
        dst[act_index(g16, kb + 1, lane)] = pack_bf16(oe[4 + o] * se, oe[5 + o] * se);
        dst[act_index(g16, kb + 2, lane)] = c < 2 ? pack_bf16(oe[8 + o] * se, oe[9 + o] * se) : pack_bf16(oo[8 + o] * so, oo[9 + o] * so);
        dst[act_index(g16, kb + 3, lane)] = pack_bf16(oo[o] * so, oo[1 + o] * so);
        dst[act_index(g16, kb + 4, lane)] = pack_bf16(oo[4 + o] * so, oo[5 + o] * so);
      }
    if (tid == 0) TS(0, 11);
    if ((tid & 127) == 0) asm volatile("cp.async.bulk.wait_group 0;" ::: "memory");
    if (tid == 0) TS(0, 6);
  }
}

namespace k2 {
constexpr uint32_t SLOT = 28672;
constexpr uint32_t Q_OFF = 7 * SLOT;
constexpr uint32_t GATE_OFF = 8 * SLOT;
constexpr uint32_t BAR_OFF = GATE_OFF + 2048;
constexpr uint32_t SMEM = BAR_OFF + 512;
constexpr uint32_t B_KVF = 0, B_FREE = 128, B_FULL = 192, B_EMPTY = 256, B_Q = 320, B_DONE = 328;
}

__device__ __forceinline__ uint32_t exp_mufu(float a, float b) { return pack_f16(ex2(a), ex2(b)); }
__device__ __forceinline__ uint32_t exp_soft(float a, float b, uint32_t half_exp) {
  uint32_t u, m, t;
  asm("cvt.pack.sat.u16.s32 %0, %1, %2;" : "=r"(u) : "r"(__float_as_uint(b)), "r"(__float_as_uint(a)));
  asm("lop3.b32 %0, %1, 0x03FF03FF, %2, 0xEA;" : "=r"(m) : "r"(u), "r"(half_exp));
  asm("fma.rn.f16x2 %0, %1, %1, %2;" : "=r"(t) : "r"(m), "r"(0x3e1f3e1fu));
  asm("fma.rn.f16x2 %0, %1, %2, %3;" : "=r"(t) : "r"(t), "r"(m), "r"(0x3a013a01u));
  return t + u - m;
}
__device__ __forceinline__ void softexp(const float (&s)[32], uint32_t (&p)[16], int half, uint32_t he) {
#pragma unroll
  for (int nb = 0; nb < 8; nb++) {
    if ((POLY_MASK >> (half * 8 + nb)) & 1) {
      p[2 * nb] = exp_soft(s[4 * nb], s[4 * nb + 1], he);
      p[2 * nb + 1] = exp_soft(s[4 * nb + 2], s[4 * nb + 3], he);
    } else {
      p[2 * nb] = exp_mufu(s[4 * nb], s[4 * nb + 1]);
      p[2 * nb + 1] = exp_mufu(s[4 * nb + 2], s[4 * nb + 3]);
    }
  }
}
__device__ __forceinline__ void mma_qk(float (&s)[32], const uint32_t (&q)[8], uint64_t base) {
  mma_rs64_bf16(s, q[0], q[1], q[2], q[3], base + (64ull << 16), 0);
  mma_rs64_bf16(s, q[4], q[5], q[6], q[7], base + 128, 1);
}
__device__ __forceinline__ void mma_pv(float (&o)[12], const uint32_t (&p)[16], uint64_t base) {
#pragma unroll
  for (int j = 0; j < 4; j++) mma_rs24_f16_t(o, p[4 * j], p[4 * j + 1], p[4 * j + 2], p[4 * j + 3], base + 192 + j * 48 + (24ull << 16), 1);
}

__device__ __forceinline__ void slow_attention(float (&o)[12], int g16, int h) {
  const int lane = threadIdx.x & 31, c = lane & 3;
  const uint4 q1 = g_q1[(h * 128 + g16) * 32 + lane];
  const uint2 q2 = g_q2[(h * 128 + g16) * 32 + lane];
  const bool aux = (h & 1) ? c < 2 : c >= 2;
  uint32_t qa[6] = {q1.x, q1.y, q1.z, q1.w, q2.x, q2.y}, qb[6];
#pragma unroll
  for (int i = 0; i < 6; i++) {
    asm("fma.rn.bf16x2 %0, %1, %2, %3;" : "=r"(qb[i]) : "r"(qa[i]), "r"(0x62806280u), "r"(0x80008000u));
    asm("fma.rn.bf16x2 %0, %0, %1, %2;" : "+r"(qb[i]) : "r"(0x62006200u), "r"(0x80008000u));
  }
  float m0 = -3e38f, m1 = -3e38f, acc[12];
  zero(acc);
  const uint32_t* kv = (const uint32_t*)g_kv + h * 32 * 1536 + lane;
#pragma unroll 1
  for (int g = 0; g < 128; g++) {
    const uint32_t* t = kv + (g >> 2) * 1536;
    float s[2][4];
    uint32_t vb[2][3];
#pragma unroll
    for (int hb = 0; hb < 2; hb++) {
      const int g8 = (g & 3) * 2 + hb;
      const bool pl = (POLY_MASK >> ((2 * g + hb) & 15)) & 1;
      const uint32_t b0 = t[g8 * 32], b1 = t[256 + g8 * 32], b2 = t[512 + g8 * 32];
      s[hb][0] = s[hb][1] = s[hb][2] = s[hb][3] = 0.f;
      asm volatile("mma.sync.aligned.m16n8k16.row.col.f32.bf16.bf16.f32 {%0,%1,%2,%3},{%4,%5,%6,%7},{%8,%9},{%0,%1,%2,%3};"
                   : "+f"(s[hb][0]), "+f"(s[hb][1]), "+f"(s[hb][2]), "+f"(s[hb][3])
                   : "r"(pl ? qb[0] : qa[0]), "r"(pl ? qb[1] : qa[1]), "r"(pl ? qb[2] : qa[2]), "r"(pl ? qb[3] : qa[3]), "r"(b0), "r"(b1));
      asm volatile("mma.sync.aligned.m16n8k8.row.col.f32.bf16.bf16.f32 {%0,%1,%2,%3},{%4,%5},{%6},{%0,%1,%2,%3};"
                   : "+f"(s[hb][0]), "+f"(s[hb][1]), "+f"(s[hb][2]), "+f"(s[hb][3])
                   : "r"(pl ? qb[4] : qa[4]), "r"(pl ? qb[5] : qa[5]), "r"(b2));
#pragma unroll
      for (int nb = 0; nb < 3; nb++)
        asm volatile("movmatrix.sync.aligned.m8n8.trans.b16 %0, %1;" : "=r"(vb[hb][nb]) : "r"(t[768 + g8 * 96 + nb * 32]));
    }
    const float n0 = fmaxf(m0, qmax(fmaxf(fmaxf(s[0][0], s[0][1]), fmaxf(s[1][0], s[1][1]))));
    const float n1 = fmaxf(m1, qmax(fmaxf(fmaxf(s[0][2], s[0][3]), fmaxf(s[1][2], s[1][3]))));
    const float a0 = ex2(m0 - n0), a1 = ex2(m1 - n1);
    m0 = n0; m1 = n1;
    const uint32_t p0 = pack_f16(ex2(s[0][0] - n0), ex2(s[0][1] - n0)), p1 = pack_f16(ex2(s[0][2] - n1), ex2(s[0][3] - n1));
    const uint32_t p2 = pack_f16(ex2(s[1][0] - n0), ex2(s[1][1] - n0)), p3 = pack_f16(ex2(s[1][2] - n1), ex2(s[1][3] - n1));
    const float vs = pow2f(((const int*)g_ve)[(h >> 2) * 128 + g]);
#pragma unroll
    for (int nb = 0; nb < 3; nb++) {
      float r0 = 0.f, r1 = 0.f, r2 = 0.f, r3 = 0.f;
      asm volatile("mma.sync.aligned.m16n8k16.row.col.f32.f16.f16.f32 {%0,%1,%2,%3},{%4,%5,%6,%7},{%8,%9},{%0,%1,%2,%3};"
                   : "+f"(r0), "+f"(r1), "+f"(r2), "+f"(r3)
                   : "r"(p0), "r"(p1), "r"(p2), "r"(p3), "r"(vb[0][nb]), "r"(vb[1][nb]));
      const float f = (nb == 2 && aux) ? 1.f : vs;
      acc[4 * nb] = fmaf(acc[4 * nb], a0, r0 * f);
      acc[4 * nb + 1] = fmaf(acc[4 * nb + 1], a0, r1 * f);
      acc[4 * nb + 2] = fmaf(acc[4 * nb + 2], a1, r2 * f);
      acc[4 * nb + 3] = fmaf(acc[4 * nb + 3], a1, r3 * f);
    }
  }
#pragma unroll
  for (int i = 0; i < 12; i++) o[i] = acc[i];
}

__global__ void __cluster_dims__(2, 1, 1) __launch_bounds__(640, 1)
k_attn(const __grid_constant__ CUtensorMap m_wob, const __grid_constant__ CUtensorMap m_woa,
       const __grid_constant__ CUtensorMap m_out) {
  using namespace k2;
  extern __shared__ __align__(1024) unsigned char smem_raw[];
  const uint32_t sb = smem_u32(smem_raw);
  const uint32_t bars = sb + BAR_OFF;
  const int tid = threadIdx.x, lane = tid & 31, warp = __shfl_sync(~0u, tid >> 5, 0);
  const uint32_t rank = blockIdx.x & 1;
  const int h = blockIdx.x >> 2, qb = blockIdx.x & 3;
  const int cid = blockIdx.x >> 1, cg = cid & 3, rbk = (cid >> 2) * 2 + rank;

  if (tid == 0) {
    TS(1, 0);
    for (int i = 0; i < 9; i++) mbar_init(bars + B_KVF + 8 * i, 1);
    for (int i = 0; i < 8; i++) {
      mbar_init(bars + B_FREE + 8 * i, 32);
      mbar_init(bars + B_FULL + 8 * i, 2);
      mbar_init(bars + B_EMPTY + 8 * i, 16);
    }
    mbar_init(bars + B_Q, 1);
    mbar_init(bars + B_Q + 16, 1);
    mbar_init(bars + B_DONE, 16);
    asm volatile("fence.mbarrier_init.release.cluster;" ::: "memory");
  }
  if (tid == 512) { prefetch_map(&m_wob); prefetch_map(&m_woa); prefetch_map(&m_out); }
  __syncwarp();
  cluster_arrive();
  cluster_wait();
  if (tid == 0) TS(1, 1);
  asm volatile("griddepcontrol.wait;" ::: "memory");
  if (tid == 0) TS(1, 2);

  if (warp >= 16) {
    asm volatile("setmaxnreg.dec.sync.aligned.u32 32;");
    if (tid == 512) {
      const unsigned char* kv = (const unsigned char*)g_kv + h * 196608;
      auto load_q = [&](int p) {
        bulk_g2s(sb + Q_OFF + p * 8192, g_q1 + (h * 128 + qb * 32 + p * 16) * 32, 8192, bars + B_Q + 16 * p);
        bulk_g2s(sb + Q_OFF + 16384 + p * 4096, g_q2 + (h * 128 + qb * 32 + p * 16) * 32, 4096, bars + B_Q + 16 * p);
      };
      mbar_expect(bars + B_Q, 12288);
      load_q(0);
      mbar_expect(bars + B_KVF, 6144);
      bulk_g2s(sb, kv, 6144, bars + B_KVF);
      for (int i = 0; i < 8; i++) {
        const uint32_t n = i < 7 ? 24576 : 18432;
        mbar_expect(bars + B_KVF + 8 + 8 * i, n);
        bulk_g2s(sb + 6144 + i * 24576, kv + 6144 + i * 24576, n, bars + B_KVF + 8 + 8 * i);
      }
      mbar_expect(bars + B_Q + 16, 12288 + 2048);
      load_q(1);
      bulk_g2s(sb + GATE_OFF, g_gate + qb * 512, 2048, bars + B_Q + 16);
      for (int i = 0; i < 20; i++) {
        const int s = (i + 7) & 7;
        if (i >= 8) mbar_wait(bars + B_EMPTY + 8 * s, ((i >> 3) - 1) & 1);
        else mbar_wait_long(bars + B_FREE + 8 * s, 0);
        mbar_expect(bars + B_FULL + 8 * s, 20480);
        tma3_mc(sb + s * SLOT + 8192 + rank * 10240, i < 10 ? &m_wob : &m_woa, 0, (i < 10 ? i : i - 10) * 64 + rank * 32, cg * 5,
                bars + B_FULL + 8 * s);
      }
    } else if (tid == 544) {
      for (int i = 0; i < 20; i++) {
        const int s = (i + 7) & 7;
        if (i >= 8) mbar_wait(bars + B_EMPTY + 8 * s, ((i >> 3) - 1) & 1);
        else mbar_wait_long(bars + B_FREE + 8 * s, 0);
        if (i == 10) {
          TS(1, 12);
          wait_count(&g_cnt[rbk], 32);
          asm volatile("fence.proxy.async.global;" ::: "memory");
          TS(1, 13);
        }
        mbar_expect(bars + B_FULL + 8 * s, 8192);
        bulk_g2s(sb + s * SLOT, g_act[i >= 10] + (rbk * 10 + (i < 10 ? i : i - 10)) * 512, 8192, bars + B_FULL + 8 * s);
      }
    } else if (tid == 576) {
      for (int p = 0; p < 2; p++) {
        mbar_wait_long(bars + B_DONE, p);
        __threadfence();
        for (int t = 0; t < 4; t++) publish(&g_cnt[qb * 8 + 4 * p + t]);
      }
    }
  } else {
    asm volatile("setmaxnreg.inc.sync.aligned.u32 112;");
    const int wg = warp >> 2, w = warp & 3, c = lane & 3, odd = h & 1;
    const bool aux = odd ? c < 2 : c >= 2;
    const uint32_t qa1 = sb + Q_OFF + warp * 512 + lane * 16, qa2 = sb + Q_OFF + 16384 + warp * 256 + lane * 8;
    uint32_t q[8], he;
    asm volatile("ld.global.b32 %0, [%3]; ld.global.b32 %1, [%3+4]; ld.global.b32 %2, [%3+8];" : "=r"(q[6]), "=r"(q[7]), "=r"(he) : "l"(g_konst));
    const float4 kn = g_kn2[h * 32 + lane];
    const int4 ve = g_ve[(h >> 2) * 32 + lane];
    const float kmax = __uint_as_float(__reduce_max_sync(~0u, __float_as_uint(fmaxf(fmaxf(kn.x, kn.y), fmaxf(kn.z, kn.w))))) * 1.02f;
    const bool vscaled = __any_sync(~0u, (ve.x | ve.y | ve.z | ve.w) != 0);
    auto load_q = [&](int pass) {
      asm volatile("ld.shared.v4.b32 {%0,%1,%2,%3}, [%4];" : "=r"(q[0]), "=r"(q[1]), "=r"(q[2]), "=r"(q[3]) : "r"(qa1 + pass * 8192) : "memory");
      asm volatile("ld.shared.v2.b32 {%0,%1}, [%2];" : "=r"(q[4]), "=r"(q[5]) : "r"(qa2 + pass * 4096) : "memory");
      float off[2];
#pragma unroll
      for (int hf = 0; hf < 2; hf++) {
        float n = 0.f;
#pragma unroll
        for (int i = 0; i < 3; i++) {
          const float a = bf_lo(q[2 * i + hf]) * 1.152921504606847e18f, b = bf_hi(q[2 * i + hf]) * 1.152921504606847e18f;
          n = fmaf(a, a, fmaf(b, b, n));
        }
        float m;
        asm("sqrt.approx.ftz.f32 %0, %1;" : "=f"(m) : "f"(qsum(n) * kmax));
        const float o = 15.49f - m;
        off[hf] = (o - fabsf(o) * 0.0078125f) * 8.673617379884035e-19f;
      }
      if (aux) {
        const float c1 = 13.25f * 8.673617379884035e-19f, c2 = 0.036215f * 8.673617379884035e-19f;
        q[4] = (c & 1) ? pack_bf16(c2, 0.f) : pack_bf16(off[0], c1);
        q[5] = (c & 1) ? pack_bf16(c2, 0.f) : pack_bf16(off[1], c1);
      }
    };
    mbar_wait(bars + B_Q, 0);
    load_q(0);
    float o[12], s[32];
    uint32_t p0[16], p1[16];
    const uint64_t base0 = mkdesc(sb, 0, 128, 0);
    zero(s); pin(s); pin(q);
    mbar_wait(bars + B_KVF, 0);
    if (tid == 0) TS(1, 5);
    wg_fence(); mma_qk(s, q, base0); wg_commit();
    wg_wait<0>(); pin(s);
#pragma unroll 1
    for (int pass = 0; pass < 2; pass++) {
      const int g16 = qb * 32 + pass * 16 + warp;
      softexp(s, p0, 0, he);
      zero(o); pin(o);
      uint64_t base = base0;
      auto step = [&](uint32_t(&pa)[16], uint32_t(&pb)[16], int t, uint32_t bar) {
        pin(s); pin(pa);
        wg_fence(); mma_qk(s, q, base + (t + 1) * 384); wg_commit();
        mma_pv(o, pa, base + t * 384); wg_commit();
        wg_wait<1>(); pin(s);
        softexp(s, pb, (t + 1) & 1, he);
        pin(s); pin(pb);
        if (t == 3) mbar_wait(bar, 0);
        wg_wait<0>(); pin(pa);
      };
      mbar_wait(bars + B_KVF + 8, 0);
#pragma unroll 1
      for (int j = 0;; j++) {
        step(p0, p1, 0, 0);
        step(p1, p0, 1, 0);
        step(p0, p1, 2, 0);
        if (j == 7) break;
        step(p1, p0, 3, bars + B_KVF + 16 + 8 * j);
        base += 4 * 384;
        if (pass && j >= 1 && lane < 2) mbar_arrive_cta(bars + B_FREE + 8 * (j - 1), lane);
      }
      pin(o);
      wg_fence(); mma_pv(o, p1, base + 3 * 384); wg_commit();
      mbar_wait(bars + B_Q + 16, 0);
      if (pass == 0) load_q(1);
      float g0, g1;
      asm volatile("ld.shared.f32 %0, [%1];" : "=f"(g0) : "r"(sb + GATE_OFF + (pass * 256 + warp * 16 + (lane >> 2)) * 4) : "memory");
      asm volatile("ld.shared.f32 %0, [%1];" : "=f"(g1) : "r"(sb + GATE_OFF + (pass * 256 + warp * 16 + 8 + (lane >> 2)) * 4) : "memory");
      wg_wait<0>(); pin(o); pin(p1);
      if (pass && lane < 2) mbar_arrive_cta(bars + B_FREE + 48, lane);
      const int ls = (lane & ~3) | (odd ? 0 : 2);
      float l0 = __shfl_sync(~0u, o[8], ls), l1 = __shfl_sync(~0u, o[10], ls);
      if (vscaled || __any_sync(~0u, !(l0 >= 128.f && l0 < 3e38f && l1 >= 128.f && l1 < 3e38f))) {
        slow_attention(o, g16, h);
        l0 = __shfl_sync(~0u, o[8], ls);
        l1 = __shfl_sync(~0u, o[10], ls);
      }
      zero(s);
      pin(s); pin(q);
      wg_fence(); mma_qk(s, q, base0); wg_commit();
      if (pass == 0 && lane < 2) mbar_arrive_cta(bars + B_FREE + 56, lane);
#pragma unroll
      for (int hf = 0; hf < 2; hf++) {
        const float sc = __fdividef(hf ? g1 : g0, hf ? l1 : l0);
        uint32_t* dst = (uint32_t*)g_act[1] + 32 * hf;
        const int kb = (h >> 1) * 5;
        dst[act_index(g16, kb + 3 * odd, lane)] = pack_bf16(o[2 * hf] * sc, o[2 * hf + 1] * sc);
        dst[act_index(g16, kb + 3 * odd + 1, lane)] = pack_bf16(o[4 + 2 * hf] * sc, o[5 + 2 * hf] * sc);
        if (!aux) dst[act_index(g16, kb + 2, lane)] = pack_bf16(o[8 + 2 * hf] * sc, o[9 + 2 * hf] * sc);
      }
      __syncwarp();
      if (lane == 0) mbar_arrive(bars + B_DONE);
      wg_wait<0>(); pin(s);
      if (tid == 0) TS(1, 6 + 2 * pass);
      if (tid == 384) TS(1, 14 + pass);
    }
    if (wg >= 2) {
      const uint32_t xaddr = sb + act_index(w, 0, lane) * 4;
      const float gb0 = 1.f - g_gate[rbk * 64 + w * 16 + (lane >> 2)], gb1 = 1.f - g_gate[rbk * 64 + w * 16 + 8 + (lane >> 2)];
      const int row = w * 16 + ((lane >> 3) & 1) * 8 + (lane & 7);
      auto gemm = [&](auto& acc, auto mma, const int nb0) {
        constexpr int NR = sizeof(acc) / sizeof(float);
        const uint64_t db0 = mkdesc(sb + 8192 + nb0 * 512, 2048, 512, 2);
        uint32_t a0[16], a1[16];
        auto load_a = [&](uint32_t(&a)[16], int i) {
          const int s = (i + 7) & 7;
          mbar_wait(bars + B_FULL + 8 * s, (i >> 3) & 1);
#pragma unroll
          for (int k = 0; k < 16; k++) asm volatile("ld.shared.b32 %0, [%1];" : "=r"(a[k]) : "r"(xaddr + s * SLOT + k * 128) : "memory");
        };
        auto stage = [&](const uint32_t(&a)[16], int i) {
          const uint64_t db = db0 + ((i + 7) & 7) * (SLOT >> 4);
          wg_fence();
#pragma unroll
          for (int k = 0; k < 4; k++) mma(acc, a[4 * k], a[4 * k + 1], a[4 * k + 2], a[4 * k + 3], db + (k >> 1) * 640 + (k & 1) * 64, 1);
          wg_commit();
        };
        zero(acc); pin(acc);
#pragma unroll 1
        for (int part = 0; part < 2; part++) {
          load_a(a0, part * 10);
          if (tid == 256 && part) TS(1, 9);
#pragma unroll 1
          for (int i = part * 10; i < part * 10 + 10; i += 2) {
            stage(a0, i);
            wg_wait<1>(); pin(a1);
            if (i != part * 10 && i <= 12 && lane < 2) mbar_arrive_cta(bars + B_EMPTY + 8 * ((i + 6) & 7), lane);
            load_a(a1, i + 1);
            stage(a1, i + 1);
            wg_wait<1>(); pin(a0);
            if (i <= 11 && lane < 2) mbar_arrive_cta(bars + B_EMPTY + 8 * ((i + 7) & 7), lane);
            if (i + 2 < part * 10 + 10) load_a(a0, i + 2);
          }
          wg_wait<0>(); pin(acc); pin(a0); pin(a1);
          if (part == 0) {
            if (lane < 2) mbar_arrive_cta(bars + B_EMPTY + 8 * ((9 + 7) & 7), lane);
#pragma unroll
            for (int i = 0; i < NR; i++) acc[i] *= (i & 2) ? gb1 : gb0;
            pin(acc);
          }
        }
        if (tid == 256) TS(1, 10);
        bar_sync(2, 256);
#pragma unroll
        for (int j = 0; j < NR / 4; j += 2) {
          const int b = nb0 + j + (lane >> 4);
          stsm4(sb + (b >> 2) * 4096 + row * 64 + (((b & 3) ^ ((row >> 1) & 3)) << 4), pack_bf16(acc[4 * j], acc[4 * j + 1]),
                pack_bf16(acc[4 * j + 2], acc[4 * j + 3]), pack_bf16(acc[4 * j + 4], acc[4 * j + 5]), pack_bf16(acc[4 * j + 6], acc[4 * j + 7]));
        }
      };
      if (wg == 2) {
        float acc[48];
        gemm(acc, [](float(&d)[48], uint32_t x0, uint32_t x1, uint32_t x2, uint32_t x3, uint64_t b, int u) { mma_rs96_bf16_t(d, x0, x1, x2, x3, b, u); }, 0);
      } else {
        float acc[32];
        gemm(acc, [](float(&d)[32], uint32_t x0, uint32_t x1, uint32_t x2, uint32_t x3, uint64_t b, int u) { mma_rs64_bf16_t(d, x0, x1, x2, x3, b, u); }, 12);
      }
      fence_async();
      bar_sync(2, 256);
      if (tid == 256) {
        asm volatile("cp.async.bulk.tensor.3d.global.shared::cta.bulk_group [%0, {%2, %3, %4}], [%1];" ::"l"(&m_out), "r"(sb),
                     "r"(0), "r"(rbk * 64), "r"(cg * 5)
                     : "memory");
        asm volatile("cp.async.bulk.commit_group;" ::: "memory");
        asm volatile("cp.async.bulk.wait_group 0;" ::: "memory");
        TS(1, 11);
      }
    }
  }
}

typedef CUresult (*EncodeFn)(CUtensorMap*, CUtensorMapDataType, cuuint32_t, void*, const cuuint64_t*, const cuuint64_t*,
                             const cuuint32_t*, const cuuint32_t*, CUtensorMapInterleave, CUtensorMapSwizzle,
                             CUtensorMapL2promotion, CUtensorMapFloatOOBfill);

CUtensorMap make_map(EncodeFn enc, const void* p, int rank, cuuint64_t d0, cuuint64_t d1, cuuint64_t d2, cuuint64_t s1,
                     cuuint64_t s2, cuuint32_t b0, cuuint32_t b1, cuuint32_t b2, CUtensorMapSwizzle sw) {
  CUtensorMap m;
  const cuuint64_t dim[3] = {d0, d1, d2}, str[2] = {s1, s2};
  const cuuint32_t box[3] = {b0, b1, b2}, es[3] = {1, 1, 1};
  enc(&m, CU_TENSOR_MAP_DATA_TYPE_BFLOAT16, rank, const_cast<void*>(p), dim, str, box, es, CU_TENSOR_MAP_INTERLEAVE_NONE, sw,
      CU_TENSOR_MAP_L2_PROMOTION_L2_128B, CU_TENSOR_MAP_FLOAT_OOB_FILL_NONE);
  return m;
}

}

extern "C" void kernel_launch(void* const* d_in, const int* in_sizes, int n_in, void* d_out, int out_size) {
  (void)in_sizes; (void)n_in; (void)out_size;
  const __nv_bfloat16* x = (const __nv_bfloat16*)d_in[0];
  EncodeFn enc = nullptr;
  cudaDriverEntryPointQueryResult qr;
  cudaGetDriverEntryPoint("cuTensorMapEncodeTiled", (void**)&enc, cudaEnableDefault, &qr);
  k1::Maps m1;
  m1.x = make_map(enc, x, 2, 640, 2048, 1, 1280, 0, 64, 128, 1, CU_TENSOR_MAP_SWIZZLE_128B);
  for (int i = 0; i < 2; i++) {
    const void* wq = d_in[i ? 4 : 1];
    m1.w1[i] = make_map(enc, wq, 3, 640, 640, 3, 3840, 1280, 64, 32, 1, CU_TENSOR_MAP_SWIZZLE_128B);
    m1.w2[i] = make_map(enc, wq, 3, 640, 640, 3, 3840, 1280, 64, 32, 2, CU_TENSOR_MAP_SWIZZLE_128B);
    m1.r1[i] = make_map(enc, wq, 3, 640, 640, 3, 3840, 1280, 16, 32, 1, CU_TENSOR_MAP_SWIZZLE_32B);
    m1.r2[i] = make_map(enc, wq, 3, 640, 640, 3, 3840, 1280, 16, 32, 2, CU_TENSOR_MAP_SWIZZLE_32B);
  }
  const CUtensorMap m_wob = make_map(enc, d_in[6], 3, 32, 640, 20, 1280, 64, 32, 32, 5, CU_TENSOR_MAP_SWIZZLE_64B);
  const CUtensorMap m_woa = make_map(enc, d_in[2], 3, 32, 640, 20, 1280, 64, 32, 32, 5, CU_TENSOR_MAP_SWIZZLE_64B);
  const CUtensorMap m_out = make_map(enc, d_out, 3, 32, 2048, 20, 1280, 64, 32, 64, 5, CU_TENSOR_MAP_SWIZZLE_64B);
  cudaFuncSetAttribute(k_qkv, cudaFuncAttributeMaxDynamicSharedMemorySize, k1::SMEM);
  cudaFuncSetAttribute(k_attn, cudaFuncAttributeMaxDynamicSharedMemorySize, k2::SMEM);

  k_qkv<<<132, 384, k1::SMEM, cudaStreamPerThread>>>(m1, x, (const __nv_bfloat16*)d_in[5], (const __nv_bfloat16*)d_in[7]);
  cudaLaunchConfig_t cfg = {};
  cfg.gridDim = dim3(128);
  cfg.blockDim = dim3(640);
  cfg.dynamicSmemBytes = k2::SMEM;
  cfg.stream = cudaStreamPerThread;
  cudaLaunchAttribute at[1];
  at[0].id = cudaLaunchAttributeProgrammaticStreamSerialization;
  at[0].val.programmaticStreamSerializationAllowed = 1;
  cfg.attrs = at;
  cfg.numAttrs = 1;
  cudaLaunchKernelEx(&cfg, k_attn, m_wob, m_woa, m_out);
}
```
